```python
import torch

def _softmax(x, axis=-1):
    return torch.softmax(x, dim=axis)
def _gelu(x):
    return torch.nn.functional.gelu(x, approximate="tanh")
def _silu(x):
    return torch.nn.functional.silu(x)
def _sigmoid(x):
    return torch.sigmoid(x)
def _layernorm(x, axis=-1, eps=1e-5):
    m = x.mean(dim=axis, keepdim=True)
    v = x.var(dim=axis, keepdim=True, unbiased=False)
    return (x - m) / torch.sqrt(v + eps)
def _scatter_add(tgt, idx, src, axis=0):
    return tgt.clone().index_add_(axis, idx, src)
def _segment_sum(src, seg, n):
    out = torch.zeros((n,) + src.shape[1:], dtype=src.dtype)
    return out.index_add_(0, seg, src)
def _pad(x, pw):
    flat = tuple(v for pair in reversed(pw) for v in pair)
    return torch.nn.functional.pad(x, flat)

kernel_name = 'concat_heads__gqa_block_cached__gqa_block_cached__near_ridge'

def setup_inputs():

    _w = (lambda a: (lambda t: t.to(torch.bfloat16) if t.is_floating_point() else t)(torch.as_tensor(a)))
    def _A_setup():
        B, Sq, D = 16, 48, 512
        Hq, Hkv, Sk, Dh = 32, 8, 1024, 128
        assert Hq % Hkv == 0, (Hq, Hkv)
        return {
            "x": _w((lambda *s: torch.randn(*s, dtype=torch.bfloat16) * 0.8)(B, Sq, D)),
            "k_cache": _w((lambda *s: torch.randn(*s, dtype=torch.bfloat16) * 0.8)(B, Hkv, Sk, Dh)),
            "v_cache": _w((lambda *s: torch.randn(*s, dtype=torch.bfloat16) * 0.05)(B, Hkv, Sk, Dh)),
            "wq": _w((lambda *s: torch.randn(*s, dtype=torch.bfloat16) * 0.8)(D, Hq * Dh) * (D ** -0.5)),
            "wo": _w((lambda *s: torch.randn(*s, dtype=torch.bfloat16) * 0.05)(Hq * Dh, D) * ((Hq * Dh) ** -0.5)),
        }
    _A_in = _A_setup()

    def _B_setup():
        B, Sq, D = 16, 48, 512
        Hq, Hkv, Sk, Dh = 32, 8, 1024, 128
        assert Hq % Hkv == 0, (Hq, Hkv)
        return {
            "x": _w((lambda *s: torch.randn(*s, dtype=torch.bfloat16) * 0.8)(B, Sq, D)),
            "k_cache": _w((lambda *s: torch.randn(*s, dtype=torch.bfloat16) * 0.8)(B, Hkv, Sk, Dh)),
            "v_cache": _w((lambda *s: torch.randn(*s, dtype=torch.bfloat16) * 0.05)(B, Hkv, Sk, Dh)),
            "wq": _w((lambda *s: torch.randn(*s, dtype=torch.bfloat16) * 0.8)(D, Hq * Dh) * (D ** -0.5)),
            "wo": _w((lambda *s: torch.randn(*s, dtype=torch.bfloat16) * 0.05)(Hq * Dh, D) * ((Hq * Dh) ** -0.5)),
        }
    _B_in = _B_setup()

    return {
        "A_x": _A_in["x"],
        "A_k_cache": _A_in["k_cache"],
        "A_v_cache": _A_in["v_cache"],
        "A_wq": _A_in["wq"],
        "A_wo": _A_in["wo"],
        "B_x": _B_in["x"],
        "B_k_cache": _B_in["k_cache"],
        "B_v_cache": _B_in["v_cache"],
        "B_wq": _B_in["wq"],
        "B_wo": _B_in["wo"],
    }

def reference(A_x, A_k_cache, A_v_cache, A_wq, A_wo, B_x, B_k_cache, B_v_cache, B_wq, B_wo):
    def _A_ref(x, k_cache, v_cache, wq, wo):
        B, Sq, D = x.shape
        Hq, Dh = 32, 128
        Hkv = k_cache.shape[1]
        rep = Hq // Hkv
        q = (lambda x, *d: x.permute(*d))((x @ wq).reshape(B, Sq, Hq, Dh), 0, 2, 1, 3)
        k = (lambda x, n, axis: torch.repeat_interleave(x, n, dim=axis))(k_cache, rep, axis=1)
        v = (lambda x, n, axis: torch.repeat_interleave(x, n, dim=axis))(v_cache, rep, axis=1)
        scores = torch.einsum("bhqd,bhkd->bhqk", q, k) * (Dh ** -0.5)
        p = _softmax(scores, axis=-1)
        o = torch.einsum("bhqk,bhkd->bhqd", p, v)
        return (lambda x, *d: x.permute(*d))(o, 0, 2, 1, 3).reshape(B, Sq, Hq * Dh) @ wo

    def _B_ref(x, k_cache, v_cache, wq, wo):
        B, Sq, D = x.shape
        Hq, Dh = 32, 128
        Hkv = k_cache.shape[1]
        rep = Hq // Hkv
        q = (lambda x, *d: x.permute(*d))((x @ wq).reshape(B, Sq, Hq, Dh), 0, 2, 1, 3)
        k = (lambda x, n, axis: torch.repeat_interleave(x, n, dim=axis))(k_cache, rep, axis=1)
        v = (lambda x, n, axis: torch.repeat_interleave(x, n, dim=axis))(v_cache, rep, axis=1)
        scores = torch.einsum("bhqd,bhkd->bhqk", q, k) * (Dh ** -0.5)
        p = _softmax(scores, axis=-1)
        o = torch.einsum("bhqk,bhkd->bhqd", p, v)
        return (lambda x, *d: x.permute(*d))(o, 0, 2, 1, 3).reshape(B, Sq, Hq * Dh) @ wo

    a = _A_ref(A_x, A_k_cache, A_v_cache, A_wq, A_wo)
    b = _B_ref(B_x, B_k_cache, B_v_cache, B_wq, B_wo)
    return torch.concatenate([a, b], axis=-1)
```

```cpp
#include <cuda_runtime.h>
#include <cuda_bf16.h>
#include <cuda.h>
#include <stdint.h>

namespace {

constexpr int SM_Q = 0;
constexpr int SM_RING = 98304;
constexpr int SM_BAR = SM_RING + 131072;
constexpr int SMEM_BYTES = SM_BAR + 512 + 1024;
constexpr int QSTAGE = 19456;
constexpr int NQS = 5;
constexpr int KV_S0 = 8, KV_SD = 5;
constexpr int B_FULL = 0, B_EMPTY = 32, B_QFULL = 64, B_QEMPTY = 104, B_WFULL = 144;

struct Params {
  CUtensorMap x[2], k[2], v[2], wq[2], wo[2];
  const __nv_bfloat16* xp[2];
  const __nv_bfloat16* wqp[2];
  const __nv_bfloat16* wop[2];
  __nv_bfloat16* out;
};

__device__ uint4 g_part[16 * 8 * 8 * 6 * 128];
#define STAMP(i)
#define CLK(k)

__device__ __forceinline__ uint32_t smem_u32(const void* p) { return (uint32_t)__cvta_generic_to_shared(p); }
__device__ __forceinline__ void mbar_init(uint32_t bar, uint32_t cnt) {
  asm volatile("mbarrier.init.shared::cta.b64 [%0], %1;" ::"r"(bar), "r"(cnt));
}
__device__ __forceinline__ void mbar_expect_tx(uint32_t bar, uint32_t bytes) {
  asm volatile("mbarrier.arrive.expect_tx.shared::cta.b64 _, [%0], %1;" ::"r"(bar), "r"(bytes) : "memory");
}
__device__ __forceinline__ void mbar_wait(uint32_t bar, uint32_t parity) {
  asm volatile(
      "{\n.reg .pred p, q;\n.reg .u32 c;\nmov.u32 c, 0;\n"
      "LAB_WAIT:\n"
      "mbarrier.try_wait.parity.shared::cta.b64 p, [%0], %1;\n"
      "@p bra LAB_DONE;\n"
      "add.u32 c, c, 1;\n"
      "setp.lt.u32 q, c, 200000;\n"
      "@q bra LAB_WAIT;\n"
      "LAB_DONE:\n}"
      ::"r"(bar), "r"(parity) : "memory");
}
__device__ __forceinline__ void mbar_arrive_local(uint32_t bar, uint32_t cnt) {
  asm volatile("mbarrier.arrive.shared::cta.b64 _, [%0], %1;" ::"r"(bar), "r"(cnt) : "memory");
}
__device__ __forceinline__ void mbar_arrive_cta(uint32_t bar, uint32_t cta, uint32_t cnt) {
  asm volatile("{\n.reg .b32 ra;\nmapa.shared::cluster.u32 ra, %0, %1;\nmbarrier.arrive.shared::cluster.b64 _, [ra], %2;\n}"
               ::"r"(bar), "r"(cta), "r"(cnt) : "memory");
}
__device__ __forceinline__ void tma2d(uint32_t dst, const CUtensorMap* m, int c0, int c1, uint32_t bar) {
  asm volatile("cp.async.bulk.tensor.2d.shared::cluster.global.mbarrier::complete_tx::bytes [%0], [%1, {%3, %4}], [%2];"
               ::"r"(dst), "l"(m), "r"(bar), "r"(c0), "r"(c1) : "memory");
}
__device__ __forceinline__ void tma3d_hint(uint32_t dst, const CUtensorMap* m, int c0, int c1, int c2, uint32_t bar, uint64_t pol) {
  asm volatile("cp.async.bulk.tensor.3d.shared::cluster.global.mbarrier::complete_tx::bytes.L2::cache_hint [%0], [%1, {%3, %4, %5}], [%2], %6;"
               ::"r"(dst), "l"(m), "r"(bar), "r"(c0), "r"(c1), "r"(c2), "l"(pol) : "memory");
}
__device__ __forceinline__ void tma2d_mc(uint32_t dst, const CUtensorMap* m, int c0, int c1, uint32_t bar) {
  asm volatile("cp.async.bulk.tensor.2d.shared::cluster.global.mbarrier::complete_tx::bytes.multicast::cluster [%0], [%1, {%3, %4}], [%2], %5;"
               ::"r"(dst), "l"(m), "r"(bar), "r"(c0), "r"(c1), "h"((uint16_t)3) : "memory");
}
__device__ __forceinline__ void tma3d_mc(uint32_t dst, const CUtensorMap* m, int c0, int c1, int c2, uint32_t bar) {
  asm volatile("cp.async.bulk.tensor.3d.shared::cluster.global.mbarrier::complete_tx::bytes.multicast::cluster [%0], [%1, {%3, %4, %5}], [%2], %6;"
               ::"r"(dst), "l"(m), "r"(bar), "r"(c0), "r"(c1), "r"(c2), "h"((uint16_t)3) : "memory");
}
__device__ __forceinline__ void prefetch_l2(const void* src, uint32_t bytes) {
  asm volatile("cp.async.bulk.prefetch.L2.global [%0], %1;" ::"l"(src), "r"(bytes) : "memory");
}
__device__ __forceinline__ void wg_fence() { asm volatile("wgmma.fence.sync.aligned;" ::: "memory"); }
__device__ __forceinline__ void wg_commit() { asm volatile("wgmma.commit_group.sync.aligned;" ::: "memory"); }
template <int N> __device__ __forceinline__ void wg_wait() { asm volatile("wgmma.wait_group.sync.aligned %0;" ::"n"(N) : "memory"); }
__device__ __forceinline__ void named_sync(int id, int n) { asm volatile("bar.sync %0, %1;" ::"r"(id), "r"(n) : "memory"); }
__device__ __forceinline__ void named_arrive(int id, int n) { asm volatile("bar.arrive %0, %1;" ::"r"(id), "r"(n) : "memory"); }
__device__ __forceinline__ void fence_async() { asm volatile("fence.proxy.async.shared::cta;" ::: "memory"); }
template <int N> __device__ __forceinline__ void reg_fence(float (&d)[N]) {
#pragma unroll
  for (int i = 0; i < N; i++) asm volatile("" : "+f"(d[i])::"memory");
}
__device__ __forceinline__ uint32_t pack_bf16(float lo, float hi) {
  uint32_t r;
  asm("cvt.rn.bf16x2.f32 %0, %1, %2;" : "=r"(r) : "f"(hi), "f"(lo));
  return r;
}
__device__ __forceinline__ float ex2(float x) {
  float r;
  asm("ex2.approx.ftz.f32 %0, %1;" : "=f"(r) : "f"(x));
  return r;
}
__device__ __forceinline__ float ex2v(float x) {
  float r;
  asm volatile("ex2.approx.ftz.f32 %0, %1;" : "=f"(r) : "f"(x));
  return r;
}
__device__ __forceinline__ void mulv(float& x, float y) { asm volatile("mul.f32 %0, %0, %1;" : "+f"(x) : "f"(y)); }
__device__ __forceinline__ void stsm4(uint32_t a, uint32_t r0, uint32_t r1, uint32_t r2, uint32_t r3) {
  asm volatile("stmatrix.sync.aligned.m8n8.x4.shared.b16 [%0], {%1, %2, %3, %4};" ::"r"(a), "r"(r0), "r"(r1), "r"(r2), "r"(r3) : "memory");
}
__device__ __forceinline__ void stsm4_t(uint32_t a, uint32_t r0, uint32_t r1, uint32_t r2, uint32_t r3) {
  asm volatile("stmatrix.sync.aligned.m8n8.x4.trans.shared.b16 [%0], {%1, %2, %3, %4};" ::"r"(a), "r"(r0), "r"(r1), "r"(r2), "r"(r3) : "memory");
}
__device__ __forceinline__ uint64_t mk_desc(uint32_t addr, uint32_t lbo, uint32_t sbo, uint32_t layout) {
  return (uint64_t)((addr & 0x3FFFF) >> 4) | ((uint64_t)(lbo >> 4) << 16) | ((uint64_t)(sbo >> 4) << 32) | ((uint64_t)layout << 62);
}

__device__ __forceinline__ void wgmma_n96_tA(float (&d)[48], uint64_t da, uint64_t db, int acc) {
  asm volatile("{\n.reg .pred p;\nsetp.ne.b32 p, %50, 0;\n"
    "wgmma.mma_async.sync.aligned.m64n96k16.f32.bf16.bf16 {%0, %1, %2, %3, %4, %5, %6, %7, %8, %9, %10, %11, %12, %13, %14, %15, %16, %17, %18, %19, %20, %21, %22, %23, %24, %25, %26, %27, %28, %29, %30, %31, %32, %33, %34, %35, %36, %37, %38, %39, %40, %41, %42, %43, %44, %45, %46, %47}, %48, %49, p, 1, 1, 1, 0;\n}\n"
    : "+f"(d[0]), "+f"(d[1]), "+f"(d[2]), "+f"(d[3]), "+f"(d[4]), "+f"(d[5]), "+f"(d[6]), "+f"(d[7]), "+f"(d[8]), "+f"(d[9]), "+f"(d[10]), "+f"(d[11]), "+f"(d[12]), "+f"(d[13]), "+f"(d[14]), "+f"(d[15]), "+f"(d[16]), "+f"(d[17]), "+f"(d[18]), "+f"(d[19]), "+f"(d[20]), "+f"(d[21]), "+f"(d[22]), "+f"(d[23]), "+f"(d[24]), "+f"(d[25]), "+f"(d[26]), "+f"(d[27]), "+f"(d[28]), "+f"(d[29]), "+f"(d[30]), "+f"(d[31]), "+f"(d[32]), "+f"(d[33]), "+f"(d[34]), "+f"(d[35]), "+f"(d[36]), "+f"(d[37]), "+f"(d[38]), "+f"(d[39]), "+f"(d[40]), "+f"(d[41]), "+f"(d[42]), "+f"(d[43]), "+f"(d[44]), "+f"(d[45]), "+f"(d[46]), "+f"(d[47])
    : "l"(da), "l"(db), "r"(acc));
}

__device__ __forceinline__ void wgmma_n128_ss(float (&d)[64], uint64_t da, uint64_t db, int acc) {
  asm volatile("{\n.reg .pred p;\nsetp.ne.b32 p, %66, 0;\n"
    "wgmma.mma_async.sync.aligned.m64n128k16.f32.bf16.bf16 {%0, %1, %2, %3, %4, %5, %6, %7, %8, %9, %10, %11, %12, %13, %14, %15, %16, %17, %18, %19, %20, %21, %22, %23, %24, %25, %26, %27, %28, %29, %30, %31, %32, %33, %34, %35, %36, %37, %38, %39, %40, %41, %42, %43, %44, %45, %46, %47, %48, %49, %50, %51, %52, %53, %54, %55, %56, %57, %58, %59, %60, %61, %62, %63}, %64, %65, p, 1, 1, 0, 0;\n}\n"
    : "+f"(d[0]), "+f"(d[1]), "+f"(d[2]), "+f"(d[3]), "+f"(d[4]), "+f"(d[5]), "+f"(d[6]), "+f"(d[7]), "+f"(d[8]), "+f"(d[9]), "+f"(d[10]), "+f"(d[11]), "+f"(d[12]), "+f"(d[13]), "+f"(d[14]), "+f"(d[15]), "+f"(d[16]), "+f"(d[17]), "+f"(d[18]), "+f"(d[19]), "+f"(d[20]), "+f"(d[21]), "+f"(d[22]), "+f"(d[23]), "+f"(d[24]), "+f"(d[25]), "+f"(d[26]), "+f"(d[27]), "+f"(d[28]), "+f"(d[29]), "+f"(d[30]), "+f"(d[31]), "+f"(d[32]), "+f"(d[33]), "+f"(d[34]), "+f"(d[35]), "+f"(d[36]), "+f"(d[37]), "+f"(d[38]), "+f"(d[39]), "+f"(d[40]), "+f"(d[41]), "+f"(d[42]), "+f"(d[43]), "+f"(d[44]), "+f"(d[45]), "+f"(d[46]), "+f"(d[47]), "+f"(d[48]), "+f"(d[49]), "+f"(d[50]), "+f"(d[51]), "+f"(d[52]), "+f"(d[53]), "+f"(d[54]), "+f"(d[55]), "+f"(d[56]), "+f"(d[57]), "+f"(d[58]), "+f"(d[59]), "+f"(d[60]), "+f"(d[61]), "+f"(d[62]), "+f"(d[63])
    : "l"(da), "l"(db), "r"(acc));
}

__device__ __forceinline__ void wgmma_n128_rs_tB(float (&d)[64], uint32_t a0, uint32_t a1, uint32_t a2, uint32_t a3, uint64_t db) {
  asm volatile("wgmma.mma_async.sync.aligned.m64n128k16.f32.bf16.bf16 {%0, %1, %2, %3, %4, %5, %6, %7, %8, %9, %10, %11, %12, %13, %14, %15, %16, %17, %18, %19, %20, %21, %22, %23, %24, %25, %26, %27, %28, %29, %30, %31, %32, %33, %34, %35, %36, %37, %38, %39, %40, %41, %42, %43, %44, %45, %46, %47, %48, %49, %50, %51, %52, %53, %54, %55, %56, %57, %58, %59, %60, %61, %62, %63}, {%64, %65, %66, %67}, %68, 1, 1, 1, 1;\n"
    : "+f"(d[0]), "+f"(d[1]), "+f"(d[2]), "+f"(d[3]), "+f"(d[4]), "+f"(d[5]), "+f"(d[6]), "+f"(d[7]), "+f"(d[8]), "+f"(d[9]), "+f"(d[10]), "+f"(d[11]), "+f"(d[12]), "+f"(d[13]), "+f"(d[14]), "+f"(d[15]), "+f"(d[16]), "+f"(d[17]), "+f"(d[18]), "+f"(d[19]), "+f"(d[20]), "+f"(d[21]), "+f"(d[22]), "+f"(d[23]), "+f"(d[24]), "+f"(d[25]), "+f"(d[26]), "+f"(d[27]), "+f"(d[28]), "+f"(d[29]), "+f"(d[30]), "+f"(d[31]), "+f"(d[32]), "+f"(d[33]), "+f"(d[34]), "+f"(d[35]), "+f"(d[36]), "+f"(d[37]), "+f"(d[38]), "+f"(d[39]), "+f"(d[40]), "+f"(d[41]), "+f"(d[42]), "+f"(d[43]), "+f"(d[44]), "+f"(d[45]), "+f"(d[46]), "+f"(d[47]), "+f"(d[48]), "+f"(d[49]), "+f"(d[50]), "+f"(d[51]), "+f"(d[52]), "+f"(d[53]), "+f"(d[54]), "+f"(d[55]), "+f"(d[56]), "+f"(d[57]), "+f"(d[58]), "+f"(d[59]), "+f"(d[60]), "+f"(d[61]), "+f"(d[62]), "+f"(d[63])
    : "r"(a0), "r"(a1), "r"(a2), "r"(a3), "l"(db));
}

__device__ __forceinline__ void wgmma_n32_tA(float (&d)[16], uint64_t da, uint64_t db, int acc) {
  asm volatile("{\n.reg .pred p;\nsetp.ne.b32 p, %18, 0;\n"
    "wgmma.mma_async.sync.aligned.m64n32k16.f32.bf16.bf16 {%0, %1, %2, %3, %4, %5, %6, %7, %8, %9, %10, %11, %12, %13, %14, %15}, %16, %17, p, 1, 1, 1, 0;\n}\n"
    : "+f"(d[0]), "+f"(d[1]), "+f"(d[2]), "+f"(d[3]), "+f"(d[4]), "+f"(d[5]), "+f"(d[6]), "+f"(d[7]), "+f"(d[8]), "+f"(d[9]), "+f"(d[10]), "+f"(d[11]), "+f"(d[12]), "+f"(d[13]), "+f"(d[14]), "+f"(d[15])
    : "l"(da), "l"(db), "r"(acc));
}

__device__ __forceinline__ void qproj(uint32_t sb, int wg, int warp, int lane) {
  float acc[2][48], acs[2][16];
  const uint32_t bar = sb + SM_BAR;
  int slot = 0, par = 0;
#pragma unroll 1
  for (int s = 0; s < 32; s++) {
    mbar_wait(bar + B_QFULL + slot * 8, par);
    if (threadIdx.x == 0 && (s & 3) == 0) STAMP(32 + s);
    const uint32_t st = sb + SM_Q + slot * QSTAGE;
    const uint64_t da = mk_desc(st, 0, 1024, 1);
    const uint64_t db = mk_desc(st + 16384, 0, 256, 3);
    wg_fence();
    wgmma_n96_tA(acc[0], da + wg * 256, db, s > 0);
    wgmma_n96_tA(acc[1], da + wg * 256 + 128, db, s > 0);
    wgmma_n32_tA(acs[0], da + 768, db + wg * 64, s > 0);
    wgmma_n32_tA(acs[1], da + 896, db + wg * 64, s > 0);
    wg_commit();
    wg_wait<1>();
    if (s > 0 && s - 1 + NQS < 32 && lane < 2) {
      int ps = slot == 0 ? NQS - 1 : slot - 1;
      mbar_arrive_cta(bar + B_QEMPTY + ps * 8, lane, 1);
    }
    if (++slot == NQS) { slot = 0; par ^= 1; }
  }
  wg_wait<0>();
  reg_fence(acc[0]); reg_fence(acc[1]); reg_fence(acs[0]); reg_fence(acs[1]);
  named_sync(1, 384);
  const int mi = lane >> 3, r8 = lane & 7;
  const uint32_t base = sb + SM_Q + r8 * 128 + (((2 * warp + (mi & 1)) ^ r8) << 4) + (mi >> 1) * 4096;
#pragma unroll
  for (int t = 0; t < 2; t++) {
#pragma unroll
    for (int c = 0; c < 12; c += 2)
      stsm4_t(base + t * 49152 + wg * 1024 + c * 4096, pack_bf16(acc[t][4 * c], acc[t][4 * c + 1]), pack_bf16(acc[t][4 * c + 2], acc[t][4 * c + 3]),
              pack_bf16(acc[t][4 * c + 4], acc[t][4 * c + 5]), pack_bf16(acc[t][4 * c + 6], acc[t][4 * c + 7]));
#pragma unroll
    for (int c = 0; c < 4; c += 2)
      stsm4_t(base + t * 49152 + 3072 + (wg * 4 + c) * 4096, pack_bf16(acs[t][4 * c], acs[t][4 * c + 1]), pack_bf16(acs[t][4 * c + 2], acs[t][4 * c + 3]),
              pack_bf16(acs[t][4 * c + 4], acs[t][4 * c + 5]), pack_bf16(acs[t][4 * c + 6], acs[t][4 * c + 7]));
  }
  fence_async();
  named_sync(1, 384);
}

__device__ __forceinline__ uint32_t pack_nz(float lo, float hi) {
  const uint32_t w = pack_bf16(lo, hi);
  return w ? w : 0x80008000u;
}
__device__ __forceinline__ void send_partial(const float (&acc)[48], int slot, int t128) {
  uint4* dst = g_part + (size_t)slot * 768 + t128;
#pragma unroll
  for (int v = 0; v < 6; v++)
    asm volatile("st.relaxed.gpu.global.v4.u32 [%0], {%1, %2, %3, %4};" ::"l"(dst + v * 128), "r"(pack_nz(acc[8 * v], acc[8 * v + 1])),
                 "r"(pack_nz(acc[8 * v + 2], acc[8 * v + 3])), "r"(pack_nz(acc[8 * v + 4], acc[8 * v + 5])),
                 "r"(pack_nz(acc[8 * v + 6], acc[8 * v + 7])) : "memory");
}

template <int NQ>
__device__ __forceinline__ void gather(float (&sum)[48], int tile, int src0, int t128) {
  uint4 t[NQ][6];
  int it = 0;
  bool ok;
  do {
#pragma unroll
    for (int q = 0; q < NQ; q++) {
      const uint4* sp = g_part + (size_t)(tile + ((src0 - q) & 7)) * 768 + t128;
#pragma unroll
      for (int v = 0; v < 6; v++)
        asm volatile("ld.relaxed.gpu.global.v4.u32 {%0, %1, %2, %3}, [%4];" : "=r"(t[q][v].x), "=r"(t[q][v].y), "=r"(t[q][v].z), "=r"(t[q][v].w)
                     : "l"(sp + v * 128) : "memory");
    }
    uint32_t mn = 0xffffffffu;
#pragma unroll
    for (int q = 0; q < NQ; q++)
#pragma unroll
      for (int v = 0; v < 6; v++) mn = min(min(mn, min(t[q][v].x, t[q][v].y)), min(t[q][v].z, t[q][v].w));
    ok = __all_sync(0xffffffffu, mn != 0);
  } while (!ok && ++it < 200000);
#pragma unroll
  for (int q = 0; q < NQ; q++) {
    uint4* sp = g_part + (size_t)(tile + ((src0 - q) & 7)) * 768 + t128;
#pragma unroll
    for (int v = 0; v < 6; v++) {
      sum[8 * v] += __uint_as_float(t[q][v].x << 16); sum[8 * v + 1] += __uint_as_float(t[q][v].x & 0xffff0000u);
      sum[8 * v + 2] += __uint_as_float(t[q][v].y << 16); sum[8 * v + 3] += __uint_as_float(t[q][v].y & 0xffff0000u);
      sum[8 * v + 4] += __uint_as_float(t[q][v].z << 16); sum[8 * v + 5] += __uint_as_float(t[q][v].z & 0xffff0000u);
      sum[8 * v + 6] += __uint_as_float(t[q][v].w << 16); sum[8 * v + 7] += __uint_as_float(t[q][v].w & 0xffff0000u);
      __stcg(sp + v * 128, make_uint4(0, 0, 0, 0));
    }
  }
}

__device__ __forceinline__ void oproj_full(float (&acc)[48], uint32_t sb, uint64_t dob, int s0) {
#pragma unroll
  for (int h = 0; h < 2; h++) {
    mbar_wait(sb + SM_BAR + B_WFULL + (12 + s0 + h) * 8, 0);
    const uint64_t da = mk_desc(sb + SM_RING + (s0 + h) * 32768, 0, 1024, 1);
    wg_fence();
#pragma unroll
    for (int kk = 0; kk < 16; kk++)
      wgmma_n96_tA(acc, da + kk * 128, dob + h * 128 + (kk >> 3) * 64 + ((kk >> 2) & 1) * 3072 + (kk & 3) * 2, (h | kk) > 0);
    wg_commit();
  }
}

__global__ void __cluster_dims__(2, 1, 1) __launch_bounds__(512, 1) gqa_fused_kernel(const __grid_constant__ Params p) {
  extern __shared__ uint8_t smem_raw[];
  const uint32_t sb = (smem_u32(smem_raw) + 1023) & ~1023u;
  const uint32_t bar = sb + SM_BAR;
  const int tid = threadIdx.x, wg = __shfl_sync(0xffffffffu, tid >> 7, 0), warp = (tid >> 5) & 3, lane = tid & 31;
  const int bpair = blockIdx.x & 7, hkv = (blockIdx.x >> 3) & 7, blk = blockIdx.x >> 6;
  const int rank = bpair & 1;

  if (tid == 0) {
    STAMP(0);
    for (int i = 0; i < 4; i++) { mbar_init(bar + B_FULL + i * 8, 1); mbar_init(bar + B_EMPTY + i * 8, 48); }
    for (int i = 0; i < NQS; i++) { mbar_init(bar + B_QFULL + i * 8, 1); mbar_init(bar + B_QEMPTY + i * 8, 24); }
    for (int i = 0; i < 16; i++) mbar_init(bar + B_WFULL + i * 8, 1);
    asm volatile("fence.mbarrier_init.release.cluster;" ::: "memory");
  }
  if (wg == 3 && warp == 0 && lane < 5) {
    const CUtensorMap* m = lane == 0 ? &p.wq[blk] : lane == 1 ? &p.x[blk] : lane == 2 ? &p.k[blk] : lane == 3 ? &p.v[blk] : &p.wo[blk];
    asm volatile("prefetch.tensormap [%0];" ::"l"(m) : "memory");
  }
  if (wg == 3 && warp == 2) {
    const __nv_bfloat16* wq = p.wqp[blk] + hkv * 512;
    prefetch_l2(wq + (size_t)(bpair + 8 * lane) * 4096, 1024);
    if (lane < 12) prefetch_l2(p.xp[blk] + (size_t)(bpair * 96 + hkv * 12 + lane) * 512, 1024);
    prefetch_l2(wq + (size_t)(bpair + 8 * (lane + 32)) * 4096, 1024);
  }
  asm volatile("barrier.cluster.arrive.relaxed.aligned;\nbarrier.cluster.wait.aligned;" ::: "memory");

  if (wg == 3) {
    asm volatile("setmaxnreg.dec.sync.aligned.u32 24;");
    if (warp == 0 && lane == 0) {
      uint64_t pol;
      asm volatile("createpolicy.fractional.L2::evict_first.b64 %0, 1.0;" : "=l"(pol));
      const int row0 = (bpair * 16 + hkv) * 1024;
      int slot = 0, par = 1, nkv = 0;
      for (int s = 0; s < 32; s++) {
        mbar_wait(bar + B_QEMPTY + slot * 8, par);
        const uint32_t st = sb + SM_Q + slot * QSTAGE, fb = bar + B_QFULL + slot * 8;
        mbar_expect_tx(fb, QSTAGE);
        tma3d_mc(st + rank * 8192, &p.wq[blk], 0, s * 16, hkv * 8 + rank * 4, fb);
        tma2d(st + 16384, &p.x[blk], s * 16, bpair * 96, fb);
        if (++slot == NQS) { slot = 0; par ^= 1; }
        if (nkv < 4 && s == KV_S0 + (hkv & 3) + KV_SD * nkv) {
          const uint32_t kb = bar + B_FULL + nkv * 8;
          mbar_expect_tx(kb, 32768);
          tma3d_hint(sb + SM_RING + nkv * 32768, (nkv & 1) ? &p.v[blk] : &p.k[blk], 0, row0 + (nkv >> 1) * 128, 0, kb, pol);
          nkv++;
        }
      }
      {
        const __nv_bfloat16* wo = p.wop[blk] + (size_t)(hkv * 512 + bpair * 64) * 512;
        for (int i = 0; i < 4; i++) prefetch_l2(wo + i * 8192, 16384);
      }
      for (int n = 4; n < 32; n++) {
        const int slot = n & 3;
        mbar_wait(bar + B_EMPTY + slot * 8, ((n >> 2) & 1) ^ 1);
        const uint32_t fb = bar + B_FULL + slot * 8;
        mbar_expect_tx(fb, 32768);
        const int row = row0 + (n >> 4) * 8192 + ((n >> 1) & 7) * 128;
        tma3d_hint(sb + SM_RING + slot * 32768, (n & 1) ? &p.v[blk] : &p.k[blk], 0, row, 0, fb, pol);
      }
      for (int i = 0; i < 16; i++) {
        const int n = 32 + i, slot = n & 3;
        mbar_wait(bar + B_EMPTY + slot * 8, ((n >> 2) & 1) ^ 1);
        const uint32_t fb = bar + B_WFULL + i * 8;
        mbar_expect_tx(fb, 32768);
        const int ti = i < 12 ? (i >> 2) * 2 + rank : (i >> 1);
        const int k0 = i < 12 ? (i & 3) * 128 : (i & 1) * 256 + rank * 128;
        tma2d_mc(sb + SM_RING + slot * 32768 + rank * 16384, &p.wo[blk], ((hkv + 1 + ti) & 7) * 64, hkv * 512 + k0, fb);
      }
    }
  } else {
    asm volatile("setmaxnreg.inc.sync.aligned.u32 160;");
    qproj(sb, wg, warp, lane);
    if (tid == 0) STAMP(1);

    const float cs = 0.08838834764831845f * 1.4426950408889634f;
    const int nxt = 3 + (wg == 0 ? 2 : wg - 1);
    if (wg == 2) { named_sync(5, 256); named_arrive(nxt, 256); }
#pragma unroll 1
    for (int u = 0; u < 2; u++) {
      float o[64];
#pragma unroll
      for (int i = 0; i < 64; i++) o[i] = 0.f;
      float m0 = -INFINITY, m1 = -INFINITY, l0 = 0.f, l1 = 0.f;
      const uint32_t qaddr = sb + SM_Q + u * 24576 + wg * 8192;
      const uint64_t dq = mk_desc(qaddr, 0, 1024, 1);
#pragma unroll 1
      for (int j = 0; j < 8; j++) {
        const int n = (u * 8 + j) * 2;
        const int ks = n & 3, vs = ks + 1, par = (n >> 2) & 1;
        const bool last = n >= 28;
        float s[64];
        mbar_wait(bar + B_FULL + ks * 8, par);
        CLK(0);
        const uint64_t dk = mk_desc(sb + SM_RING + ks * 32768, 0, 1024, 1);
        if (wg != 0 || n != 0) named_sync(3 + wg, 256);
        CLK(1);
        wg_fence();
#pragma unroll
        for (int kk = 0; kk < 8; kk++)
          wgmma_n128_ss(s, dq + (kk >> 2) * 3072 + (kk & 3) * 2, dk + (kk >> 2) * 1024 + (kk & 3) * 2, kk > 0);
        wg_commit();
        named_arrive(nxt, 256);
        CLK(2);
        wg_wait<0>();
        reg_fence(s);
        CLK(3);
        if (last) { if (lane < 2) mbar_arrive_cta(bar + B_EMPTY + ks * 8, lane, 2); }
        else if (lane == 0) mbar_arrive_local(bar + B_EMPTY + ks * 8, 4);

        float xa = fmaxf(s[0], m0), xb = s[1], xc = fmaxf(s[2], m1), xd = s[3];
#pragma unroll
        for (int c = 1; c < 16; c++) {
          xa = fmaxf(xa, s[4 * c]); xb = fmaxf(xb, s[4 * c + 1]);
          xc = fmaxf(xc, s[4 * c + 2]); xd = fmaxf(xd, s[4 * c + 3]);
        }
        float mn0 = fmaxf(xa, xb), mn1 = fmaxf(xc, xd);
        mn0 = fmaxf(mn0, __shfl_xor_sync(0xffffffffu, mn0, 1));
        mn1 = fmaxf(mn1, __shfl_xor_sync(0xffffffffu, mn1, 1));
        mn0 = fmaxf(mn0, __shfl_xor_sync(0xffffffffu, mn0, 2));
        mn1 = fmaxf(mn1, __shfl_xor_sync(0xffffffffu, mn1, 2));
        const float nb0 = -mn0 * cs, nb1 = -mn1 * cs;
        const float sc0 = ex2v(fmaf(m0, cs, nb0)), sc1 = ex2v(fmaf(m1, cs, nb1));
        m0 = mn0; m1 = mn1;
        uint32_t pr[32];
        float e0 = ex2v(fmaf(s[0], cs, nb0)), e1 = ex2v(fmaf(s[1], cs, nb0));
        float e2 = ex2v(fmaf(s[2], cs, nb1)), e3 = ex2v(fmaf(s[3], cs, nb1));
        l0 *= sc0; l1 *= sc1;
        float l2 = 0.f, l3 = 0.f;
#pragma unroll
        for (int c = 0; c < 16; c++) {
          float f0, f1, f2, f3;
          if (c < 15) {
            f0 = ex2v(fmaf(s[4 * c + 4], cs, nb0)); f1 = ex2v(fmaf(s[4 * c + 5], cs, nb0));
            f2 = ex2v(fmaf(s[4 * c + 6], cs, nb1)); f3 = ex2v(fmaf(s[4 * c + 7], cs, nb1));
          }
          mulv(o[4 * c], sc0); mulv(o[4 * c + 1], sc0);
          mulv(o[4 * c + 2], sc1); mulv(o[4 * c + 3], sc1);
          l0 += e0; l2 += e1; l1 += e2; l3 += e3;
          pr[2 * c] = pack_bf16(e0, e1);
          pr[2 * c + 1] = pack_bf16(e2, e3);
          e0 = f0; e1 = f1; e2 = f2; e3 = f3;
        }
        l0 += l2; l1 += l3;
        reg_fence(o);
        CLK(4);
        mbar_wait(bar + B_FULL + vs * 8, par);
        CLK(5);
        const uint64_t dv = mk_desc(sb + SM_RING + vs * 32768, 16384, 1024, 1);
        reg_fence(o);
        if (wg != 2 || n != 30) named_sync(3 + wg, 256);
        wg_fence();
#pragma unroll
        for (int kk = 0; kk < 8; kk++)
          wgmma_n128_rs_tB(o, pr[4 * kk], pr[4 * kk + 1], pr[4 * kk + 2], pr[4 * kk + 3], dv + kk * 128);
        wg_commit();
        if (wg == 0 || n != 30) named_arrive(nxt, 256);
        CLK(6);
        wg_wait<0>();
        reg_fence(o);
        CLK(7);
        if (last) { if (lane < 2) mbar_arrive_cta(bar + B_EMPTY + vs * 8, lane, 2); }
        else if (lane == 0) mbar_arrive_local(bar + B_EMPTY + vs * 8, 4);
        if (tid == 0) STAMP(8 + u * 8 + j);
      }
      l0 += __shfl_xor_sync(0xffffffffu, l0, 1);
      l1 += __shfl_xor_sync(0xffffffffu, l1, 1);
      l0 += __shfl_xor_sync(0xffffffffu, l0, 2);
      l1 += __shfl_xor_sync(0xffffffffu, l1, 2);
      const float i0 = 1.f / l0, i1 = 1.f / l1;
      const int mi = lane >> 3, r8 = lane & 7;
      const uint32_t obase = qaddr + (warp * 16 + (mi & 1) * 8 + r8) * 128;
#pragma unroll
      for (int c = 0; c < 16; c += 2) {
        const int ch = (c & 7) + (mi >> 1);
        stsm4(obase + (c >> 3) * 49152 + ((ch ^ r8) << 4),
              pack_bf16(o[4 * c] * i0, o[4 * c + 1] * i0), pack_bf16(o[4 * c + 2] * i1, o[4 * c + 3] * i1),
              pack_bf16(o[4 * c + 4] * i0, o[4 * c + 5] * i0), pack_bf16(o[4 * c + 6] * i1, o[4 * c + 7] * i1));
      }
    }
    fence_async();
    named_sync(1, 384);
    if (tid == 0) STAMP(2);

    const int bp = blk * 8 + bpair;
    const int t128 = tid & 127;
    const uint64_t dob = mk_desc(sb + SM_Q, 0, 4096, 1);
#pragma unroll 1
    for (int i = wg; i < 6; i += 3) {
      float acc[48];
#pragma unroll
      for (int c = 0; c < 4; c++) {
        mbar_wait(bar + B_WFULL + ((i >> 1) * 4 + c) * 8, 0);
        if (i == 0 && t128 == 0) STAMP(33 + c + (c == 3));
        const uint64_t da = mk_desc(sb + SM_RING + c * 32768 + (i & 1) * 16384, 0, 1024, 1);
        wg_fence();
#pragma unroll
        for (int kk = 0; kk < 8; kk++)
          wgmma_n96_tA(acc, da + kk * 128, dob + c * 64 + (kk >> 2) * 3072 + (kk & 3) * 2, (c | kk) > 0);
        wg_commit();
        if (c > 0) {
          wg_wait<1>();
          if (lane < 2) mbar_arrive_cta(bar + B_EMPTY + (c - 1) * 8, lane, 3);
        }
      }
      wg_wait<0>();
      reg_fence(acc);
      if (lane < 2) mbar_arrive_cta(bar + B_EMPTY + 3 * 8, lane, 3);
      if (t128 == 0) STAMP(24 + i);
      send_partial(acc, (bp * 8 + ((hkv + 1 + i) & 7)) * 8 + hkv, t128);
    }
    if (wg == 0) {
      float acc[48];
      oproj_full(acc, sb, dob, 0);
      named_arrive(6, 256);
      wg_wait<0>();
      reg_fence(acc);
      send_partial(acc, (bp * 8 + ((hkv + 7) & 7)) * 8 + hkv, t128);
      if (t128 == 0) STAMP(6);
    } else if (wg == 1) {
      float acc[48], sum[48];
#pragma unroll
      for (int v = 0; v < 48; v++) sum[v] = 0.f;
      const int tile = (bp * 8 + hkv) * 8;
      gather<2>(sum, tile, hkv + 7, t128);
      gather<2>(sum, tile, hkv + 5, t128);
      named_sync(6, 256);
      oproj_full(acc, sb, dob, 2);
      if (t128 == 0) STAMP(3);
      gather<1>(sum, tile, hkv + 3, t128);
      gather<1>(sum, tile, hkv + 2, t128);
      gather<1>(sum, tile, hkv + 1, t128);
      if (t128 == 0) STAMP(4);
      wg_wait<0>();
      reg_fence(acc);
#pragma unroll
      for (int v = 0; v < 48; v++) acc[v] += sum[v];
      named_sync(2, 128);
      const uint32_t stg = sb + SM_RING + 2 * 32768;
      const int mi = lane >> 3, r8 = lane & 7;
      const uint32_t base = stg + r8 * 128 + (((2 * warp + (mi & 1)) ^ r8) << 4) + (mi >> 1) * 1024;
#pragma unroll
      for (int c = 0; c < 12; c += 2)
        stsm4_t(base + c * 1024, pack_bf16(acc[4 * c], acc[4 * c + 1]), pack_bf16(acc[4 * c + 2], acc[4 * c + 3]),
                pack_bf16(acc[4 * c + 4], acc[4 * c + 5]), pack_bf16(acc[4 * c + 6], acc[4 * c + 7]));
      named_sync(2, 128);
#pragma unroll
      for (int it = 0; it < 6; it++) {
        const int idx = it * 128 + t128, row = idx >> 3, ch = idx & 7;
        uint4 v;
        asm volatile("ld.shared.v4.u32 {%0, %1, %2, %3}, [%4];" : "=r"(v.x), "=r"(v.y), "=r"(v.z), "=r"(v.w)
                     : "r"(stg + row * 128 + ((ch ^ (row & 7)) << 4)));
        *reinterpret_cast<uint4*>(p.out + (size_t)(bpair * 96 + row) * 1024 + blk * 512 + hkv * 64 + ch * 8) = v;
      }
      if (t128 == 0) STAMP(5);
    }
  }
}

typedef CUresult (*EncodeFn)(CUtensorMap*, CUtensorMapDataType, cuuint32_t, void*, const cuuint64_t*, const cuuint64_t*,
                             const cuuint32_t*, const cuuint32_t*, CUtensorMapInterleave, CUtensorMapSwizzle,
                             CUtensorMapL2promotion, CUtensorMapFloatOOBfill);

void encode(EncodeFn enc, CUtensorMap* m, const void* ptr, int rank, const cuuint64_t* dims, const cuuint64_t* strides,
            const cuuint32_t* box, CUtensorMapSwizzle sw) {
  cuuint32_t es[3] = {1, 1, 1};
  enc(m, CU_TENSOR_MAP_DATA_TYPE_BFLOAT16, rank, const_cast<void*>(ptr), dims, strides, box, es, CU_TENSOR_MAP_INTERLEAVE_NONE, sw,
      CU_TENSOR_MAP_L2_PROMOTION_L2_128B, CU_TENSOR_MAP_FLOAT_OOB_FILL_NONE);
}

}

extern "C" void kernel_launch(void* const* d_in, const int* in_sizes, int n_in, void* d_out, int out_size) {
  (void)in_sizes; (void)n_in; (void)out_size;
  static EncodeFn enc = nullptr;
  if (!enc) {
    cudaDriverEntryPointQueryResult qr;
    cudaGetDriverEntryPoint("cuTensorMapEncodeTiled", (void**)&enc, cudaEnableDefault, &qr);
    cudaFuncSetAttribute(gqa_fused_kernel, cudaFuncAttributeMaxDynamicSharedMemorySize, SMEM_BYTES);
  }
  Params p;
  for (int b = 0; b < 2; b++) {
    const void* x = d_in[b * 5 + 0];
    const void* k = d_in[b * 5 + 1];
    const void* v = d_in[b * 5 + 2];
    const void* wq = d_in[b * 5 + 3];
    const void* wo = d_in[b * 5 + 4];
    {
      cuuint64_t d[2] = {512, 768}, s[1] = {1024};
      cuuint32_t bx[2] = {16, 96};
      encode(enc, &p.x[b], x, 2, d, s, bx, CU_TENSOR_MAP_SWIZZLE_32B);
    }
    {
      cuuint64_t d[3] = {64, 131072, 2}, s[2] = {256, 128};
      cuuint32_t bx[3] = {64, 128, 2};
      encode(enc, &p.k[b], k, 3, d, s, bx, CU_TENSOR_MAP_SWIZZLE_128B);
      encode(enc, &p.v[b], v, 3, d, s, bx, CU_TENSOR_MAP_SWIZZLE_128B);
    }
    {
      cuuint64_t d[3] = {64, 512, 64}, s[2] = {8192, 128};
      cuuint32_t bx[3] = {64, 16, 4};
      encode(enc, &p.wq[b], wq, 3, d, s, bx, CU_TENSOR_MAP_SWIZZLE_128B);
    }
    {
      cuuint64_t d[2] = {512, 4096}, s[1] = {1024};
      cuuint32_t bx[2] = {64, 128};
      encode(enc, &p.wo[b], wo, 2, d, s, bx, CU_TENSOR_MAP_SWIZZLE_128B);
    }
    p.xp[b] = (const __nv_bfloat16*)x;
    p.wqp[b] = (const __nv_bfloat16*)wq;
    p.wop[b] = (const __nv_bfloat16*)wo;
  }
  p.out = (__nv_bfloat16*)d_out;
  gqa_fused_kernel<<<128, 512, SMEM_BYTES, cudaStreamPerThread>>>(p);
}
```

```cpp
#include <cuda_runtime.h>
#include <cuda_bf16.h>
#include <cuda.h>
#include <stdint.h>

namespace {

constexpr uint32_t SM_BASE = 1024;
constexpr int SM_Q = 0;
constexpr int SM_RING = 98304;
constexpr int SM_BAR = SM_RING + 131072;
constexpr int SMEM_BYTES = SM_BAR + 1024;
constexpr int QSTAGE = 19456;
constexpr int NQS = 11;
constexpr int SM_XQ = SM_Q + 49152;
#define PACE_T0 7500
#define PACE_ST 80
#define PACE_DT 1400
#define WO_DT 120
#define PF_T0 600
#define CLR_N 26
#define PF_EARLY 4
#define PF_NKV 16
#define PF_DT0 160
#define PF_DT 164
constexpr int B_FULL = 0, B_EMPTY = 160, B_QFULL = 64, B_QEMPTY = 784, B_SFREE = 880, B_NLOAD = 240, B_WFULL = 256, B_WEMPTY = 512;

struct Params {
  CUtensorMap x[2], k[2], v[2], wq[2], wo[2], mo;
  const __nv_bfloat16* xp[2];
  const __nv_bfloat16* wqp[2];
  const __nv_bfloat16* wop[2];
  const __nv_bfloat16* kp[2];
  const __nv_bfloat16* vp[2];
  __nv_bfloat16* out;
};

__device__ unsigned int g_cleared[16];
#define STAMP(i)

__device__ __forceinline__ uint32_t smem_u32(const void* p) { return (uint32_t)__cvta_generic_to_shared(p); }
__device__ __forceinline__ void mbar_init(uint32_t bar, uint32_t cnt) {
  asm volatile("mbarrier.init.shared::cta.b64 [%0], %1;" ::"r"(bar), "r"(cnt));
}
__device__ __forceinline__ void mbar_expect_tx(uint32_t bar, uint32_t bytes) {
  asm volatile("mbarrier.arrive.expect_tx.shared::cta.b64 _, [%0], %1;" ::"r"(bar), "r"(bytes) : "memory");
}
__device__ __forceinline__ void mbar_wait(uint32_t bar, uint32_t parity) {
  asm volatile(
      "{\n.reg .pred p, q;\n.reg .u32 c;\nmov.u32 c, 0;\n"
      "LAB_WAIT:\n"
      "mbarrier.try_wait.parity.shared::cta.b64 p, [%0], %1;\n"
      "@p bra LAB_DONE;\n"
      "add.u32 c, c, 1;\n"
      "setp.lt.u32 q, c, 200000;\n"
      "@q bra LAB_WAIT;\n"
      "LAB_DONE:\n}"
      ::"r"(bar), "r"(parity) : "memory");
}
__device__ __forceinline__ void mbar_arrive_local(uint32_t bar, uint32_t cnt) {
  asm volatile("mbarrier.arrive.shared::cta.b64 _, [%0], %1;" ::"r"(bar), "r"(cnt) : "memory");
}
__device__ __forceinline__ void mbar_arrive_cta(uint32_t bar, uint32_t cta, uint32_t cnt) {
  asm volatile("{\n.reg .b32 ra;\nmapa.shared::cluster.u32 ra, %0, %1;\nmbarrier.arrive.shared::cluster.b64 _, [ra], %2;\n}"
               ::"r"(bar), "r"(cta), "r"(cnt) : "memory");
}
__device__ __forceinline__ uint32_t gtime() {
  uint32_t t;
  asm volatile("mov.u32 %0, %%globaltimer_lo;" : "=r"(t));
  return t;
}
__device__ __forceinline__ void wait_until(uint32_t t) {
  for (int it = 0; it < 100000 && (int)(gtime() - t) < 0; it++) {}
}
__device__ __forceinline__ void wait_nload(uint32_t bar, uint32_t n) {
  for (int it = 0; it < 100000; it++) {
    uint32_t nl;
    asm volatile("ld.volatile.shared.u32 %0, [%1];" : "=r"(nl) : "r"(bar + B_NLOAD) : "memory");
    if (nl >= n) break;
    __nanosleep(100);
  }
}
__device__ __forceinline__ void tma2d(uint32_t dst, const CUtensorMap* m, int c0, int c1, uint32_t bar) {
  asm volatile("cp.async.bulk.tensor.2d.shared::cluster.global.mbarrier::complete_tx::bytes [%0], [%1, {%3, %4}], [%2];"
               ::"r"(dst), "l"(m), "r"(bar), "r"(c0), "r"(c1) : "memory");
}
__device__ __forceinline__ void tma3d_hint(uint32_t dst, const CUtensorMap* m, int c0, int c1, int c2, uint32_t bar, uint64_t pol) {
  asm volatile("cp.async.bulk.tensor.3d.shared::cluster.global.mbarrier::complete_tx::bytes.L2::cache_hint [%0], [%1, {%3, %4, %5}], [%2], %6;"
               ::"r"(dst), "l"(m), "r"(bar), "r"(c0), "r"(c1), "r"(c2), "l"(pol) : "memory");
}
__device__ __forceinline__ void tma2d_mc(uint32_t dst, const CUtensorMap* m, int c0, int c1, uint32_t bar) {
  asm volatile("cp.async.bulk.tensor.2d.shared::cluster.global.mbarrier::complete_tx::bytes.multicast::cluster [%0], [%1, {%3, %4}], [%2], %5;"
               ::"r"(dst), "l"(m), "r"(bar), "r"(c0), "r"(c1), "h"((uint16_t)3) : "memory");
}
__device__ __forceinline__ void tma3d_mc(uint32_t dst, const CUtensorMap* m, int c0, int c1, int c2, uint32_t bar) {
  asm volatile("cp.async.bulk.tensor.3d.shared::cluster.global.mbarrier::complete_tx::bytes.multicast::cluster [%0], [%1, {%3, %4, %5}], [%2], %6;"
               ::"r"(dst), "l"(m), "r"(bar), "r"(c0), "r"(c1), "r"(c2), "h"((uint16_t)3) : "memory");
}
__device__ __forceinline__ void pf_l2(const void* a) { asm volatile("prefetch.global.L2 [%0];" ::"l"(a) : "memory"); }
__device__ __forceinline__ void wg_fence() { asm volatile("wgmma.fence.sync.aligned;" ::: "memory"); }
__device__ __forceinline__ void wg_commit() { asm volatile("wgmma.commit_group.sync.aligned;" ::: "memory"); }
template <int N> __device__ __forceinline__ void wg_wait() { asm volatile("wgmma.wait_group.sync.aligned %0;" ::"n"(N) : "memory"); }
__device__ __forceinline__ void named_sync(int id, int n) { asm volatile("bar.sync %0, %1;" ::"r"(id), "r"(n) : "memory"); }
__device__ __forceinline__ void named_arrive(int id, int n) { asm volatile("bar.arrive %0, %1;" ::"r"(id), "r"(n) : "memory"); }
__device__ __forceinline__ void fence_async() { asm volatile("fence.proxy.async.shared::cta;" ::: "memory"); }
template <int N> __device__ __forceinline__ void reg_fence(float (&d)[N]) {
#pragma unroll
  for (int i = 0; i < N; i++) asm volatile("" : "+f"(d[i])::"memory");
}
__device__ __forceinline__ uint32_t pack_bf16(float lo, float hi) {
  uint32_t r;
  asm("cvt.rn.bf16x2.f32 %0, %1, %2;" : "=r"(r) : "f"(hi), "f"(lo));
  return r;
}
__device__ __forceinline__ float ex2v(float x) {
  float r;
  asm volatile("ex2.approx.ftz.f32 %0, %1;" : "=f"(r) : "f"(x));
  return r;
}
__device__ __forceinline__ void mulv(float& x, float y) { asm volatile("mul.f32 %0, %0, %1;" : "+f"(x) : "f"(y)); }
__device__ __forceinline__ void stsm4(uint32_t a, uint32_t r0, uint32_t r1, uint32_t r2, uint32_t r3) {
  asm volatile("stmatrix.sync.aligned.m8n8.x4.shared.b16 [%0], {%1, %2, %3, %4};" ::"r"(a), "r"(r0), "r"(r1), "r"(r2), "r"(r3) : "memory");
}
__device__ __forceinline__ void stsm4_t(uint32_t a, uint32_t r0, uint32_t r1, uint32_t r2, uint32_t r3) {
  asm volatile("stmatrix.sync.aligned.m8n8.x4.trans.shared.b16 [%0], {%1, %2, %3, %4};" ::"r"(a), "r"(r0), "r"(r1), "r"(r2), "r"(r3) : "memory");
}
__device__ __forceinline__ uint64_t mk_desc(uint32_t addr, uint32_t lbo, uint32_t sbo, uint32_t layout) {
  return (uint64_t)((SM_BASE + addr) >> 4) + ((uint64_t)(lbo >> 4) << 16) + ((uint64_t)(sbo >> 4) << 32) + ((uint64_t)layout << 62);
}

__device__ __forceinline__ void wgmma_n96_tA(float (&d)[48], uint64_t da, uint64_t db, int acc) {
  asm volatile("{\n.reg .pred p;\nsetp.ne.b32 p, %50, 0;\n"
    "wgmma.mma_async.sync.aligned.m64n96k16.f32.bf16.bf16 {%0, %1, %2, %3, %4, %5, %6, %7, %8, %9, %10, %11, %12, %13, %14, %15, %16, %17, %18, %19, %20, %21, %22, %23, %24, %25, %26, %27, %28, %29, %30, %31, %32, %33, %34, %35, %36, %37, %38, %39, %40, %41, %42, %43, %44, %45, %46, %47}, %48, %49, p, 1, 1, 1, 0;\n}\n"
    : "+f"(d[0]), "+f"(d[1]), "+f"(d[2]), "+f"(d[3]), "+f"(d[4]), "+f"(d[5]), "+f"(d[6]), "+f"(d[7]), "+f"(d[8]), "+f"(d[9]), "+f"(d[10]), "+f"(d[11]), "+f"(d[12]), "+f"(d[13]), "+f"(d[14]), "+f"(d[15]), "+f"(d[16]), "+f"(d[17]), "+f"(d[18]), "+f"(d[19]), "+f"(d[20]), "+f"(d[21]), "+f"(d[22]), "+f"(d[23]), "+f"(d[24]), "+f"(d[25]), "+f"(d[26]), "+f"(d[27]), "+f"(d[28]), "+f"(d[29]), "+f"(d[30]), "+f"(d[31]), "+f"(d[32]), "+f"(d[33]), "+f"(d[34]), "+f"(d[35]), "+f"(d[36]), "+f"(d[37]), "+f"(d[38]), "+f"(d[39]), "+f"(d[40]), "+f"(d[41]), "+f"(d[42]), "+f"(d[43]), "+f"(d[44]), "+f"(d[45]), "+f"(d[46]), "+f"(d[47])
    : "l"(da), "l"(db), "r"(acc));
}

__device__ __forceinline__ void wgmma_n128_ss(float (&d)[64], uint64_t da, uint64_t db, int acc) {
  asm volatile("{\n.reg .pred p;\nsetp.ne.b32 p, %66, 0;\n"
    "wgmma.mma_async.sync.aligned.m64n128k16.f32.bf16.bf16 {%0, %1, %2, %3, %4, %5, %6, %7, %8, %9, %10, %11, %12, %13, %14, %15, %16, %17, %18, %19, %20, %21, %22, %23, %24, %25, %26, %27, %28, %29, %30, %31, %32, %33, %34, %35, %36, %37, %38, %39, %40, %41, %42, %43, %44, %45, %46, %47, %48, %49, %50, %51, %52, %53, %54, %55, %56, %57, %58, %59, %60, %61, %62, %63}, %64, %65, p, 1, 1, 0, 0;\n}\n"
    : "+f"(d[0]), "+f"(d[1]), "+f"(d[2]), "+f"(d[3]), "+f"(d[4]), "+f"(d[5]), "+f"(d[6]), "+f"(d[7]), "+f"(d[8]), "+f"(d[9]), "+f"(d[10]), "+f"(d[11]), "+f"(d[12]), "+f"(d[13]), "+f"(d[14]), "+f"(d[15]), "+f"(d[16]), "+f"(d[17]), "+f"(d[18]), "+f"(d[19]), "+f"(d[20]), "+f"(d[21]), "+f"(d[22]), "+f"(d[23]), "+f"(d[24]), "+f"(d[25]), "+f"(d[26]), "+f"(d[27]), "+f"(d[28]), "+f"(d[29]), "+f"(d[30]), "+f"(d[31]), "+f"(d[32]), "+f"(d[33]), "+f"(d[34]), "+f"(d[35]), "+f"(d[36]), "+f"(d[37]), "+f"(d[38]), "+f"(d[39]), "+f"(d[40]), "+f"(d[41]), "+f"(d[42]), "+f"(d[43]), "+f"(d[44]), "+f"(d[45]), "+f"(d[46]), "+f"(d[47]), "+f"(d[48]), "+f"(d[49]), "+f"(d[50]), "+f"(d[51]), "+f"(d[52]), "+f"(d[53]), "+f"(d[54]), "+f"(d[55]), "+f"(d[56]), "+f"(d[57]), "+f"(d[58]), "+f"(d[59]), "+f"(d[60]), "+f"(d[61]), "+f"(d[62]), "+f"(d[63])
    : "l"(da), "l"(db), "r"(acc));
}

__device__ __forceinline__ void wgmma_n128_rs_tB(float (&d)[64], uint32_t a0, uint32_t a1, uint32_t a2, uint32_t a3, uint64_t db, int acc) {
  asm volatile("{\n.reg .pred p;\nsetp.ne.b32 p, %69, 0;\n"
    "wgmma.mma_async.sync.aligned.m64n128k16.f32.bf16.bf16 {%0, %1, %2, %3, %4, %5, %6, %7, %8, %9, %10, %11, %12, %13, %14, %15, %16, %17, %18, %19, %20, %21, %22, %23, %24, %25, %26, %27, %28, %29, %30, %31, %32, %33, %34, %35, %36, %37, %38, %39, %40, %41, %42, %43, %44, %45, %46, %47, %48, %49, %50, %51, %52, %53, %54, %55, %56, %57, %58, %59, %60, %61, %62, %63}, {%64, %65, %66, %67}, %68, p, 1, 1, 1;\n}\n"
    : "+f"(d[0]), "+f"(d[1]), "+f"(d[2]), "+f"(d[3]), "+f"(d[4]), "+f"(d[5]), "+f"(d[6]), "+f"(d[7]), "+f"(d[8]), "+f"(d[9]), "+f"(d[10]), "+f"(d[11]), "+f"(d[12]), "+f"(d[13]), "+f"(d[14]), "+f"(d[15]), "+f"(d[16]), "+f"(d[17]), "+f"(d[18]), "+f"(d[19]), "+f"(d[20]), "+f"(d[21]), "+f"(d[22]), "+f"(d[23]), "+f"(d[24]), "+f"(d[25]), "+f"(d[26]), "+f"(d[27]), "+f"(d[28]), "+f"(d[29]), "+f"(d[30]), "+f"(d[31]), "+f"(d[32]), "+f"(d[33]), "+f"(d[34]), "+f"(d[35]), "+f"(d[36]), "+f"(d[37]), "+f"(d[38]), "+f"(d[39]), "+f"(d[40]), "+f"(d[41]), "+f"(d[42]), "+f"(d[43]), "+f"(d[44]), "+f"(d[45]), "+f"(d[46]), "+f"(d[47]), "+f"(d[48]), "+f"(d[49]), "+f"(d[50]), "+f"(d[51]), "+f"(d[52]), "+f"(d[53]), "+f"(d[54]), "+f"(d[55]), "+f"(d[56]), "+f"(d[57]), "+f"(d[58]), "+f"(d[59]), "+f"(d[60]), "+f"(d[61]), "+f"(d[62]), "+f"(d[63])
    : "r"(a0), "r"(a1), "r"(a2), "r"(a3), "l"(db), "r"(acc));
}

__device__ __forceinline__ void wgmma_n32_tA(float (&d)[16], uint64_t da, uint64_t db, int acc) {
  asm volatile("{\n.reg .pred p;\nsetp.ne.b32 p, %18, 0;\n"
    "wgmma.mma_async.sync.aligned.m64n32k16.f32.bf16.bf16 {%0, %1, %2, %3, %4, %5, %6, %7, %8, %9, %10, %11, %12, %13, %14, %15}, %16, %17, p, 1, 1, 1, 0;\n}\n"
    : "+f"(d[0]), "+f"(d[1]), "+f"(d[2]), "+f"(d[3]), "+f"(d[4]), "+f"(d[5]), "+f"(d[6]), "+f"(d[7]), "+f"(d[8]), "+f"(d[9]), "+f"(d[10]), "+f"(d[11]), "+f"(d[12]), "+f"(d[13]), "+f"(d[14]), "+f"(d[15])
    : "l"(da), "l"(db), "r"(acc));
}

__device__ __forceinline__ void qproj(uint32_t sb, int wg, int warp, int lane) {
  float acc[2][48], acs[2][16];
  const uint32_t bar = sb + SM_BAR;
  int slot = 1, par = 0;
#pragma unroll 1
  for (int s = 0; s < 32; s++) {
    const uint64_t da = mk_desc((slot < 8 ? SM_RING : SM_Q - 131072) + slot * 16384, 0, 1024, 1);
    const uint64_t db = mk_desc(SM_XQ + slot * 3072, 0, 256, 3);
    mbar_wait(bar + B_QFULL + slot * 8, par);
    if (threadIdx.x == 0 && (s & 7) == 0) STAMP(s == 0 ? 32 : 60 + (s >> 3));
    wg_fence();
    wgmma_n96_tA(acc[0], da + wg * 256, db, s > 0);
    wgmma_n96_tA(acc[1], da + wg * 256 + 128, db, s > 0);
    wgmma_n32_tA(acs[0], da + 768, db + wg * 64, s > 0);
    wgmma_n32_tA(acs[1], da + 896, db + wg * 64, s > 0);
    wg_commit();
    wg_wait<0>();
    if (s < 29 && lane < 2) mbar_arrive_cta(bar + B_QEMPTY + slot * 8, lane, 1);
    if (++slot == NQS) slot = 0;
    if (slot == 1) par ^= 1;
  }
  reg_fence(acc[0]); reg_fence(acc[1]); reg_fence(acs[0]); reg_fence(acs[1]);
  named_sync(1, 384);
  const int mi = lane >> 3, r8 = lane & 7;
  const uint32_t base = sb + SM_Q + r8 * 128 + (((2 * warp + (mi & 1)) ^ r8) << 4) + (mi >> 1) * 4096;
#pragma unroll
  for (int t = 0; t < 2; t++) {
#pragma unroll
    for (int c = 0; c < 12; c += 2)
      stsm4_t(base + t * 49152 + wg * 1024 + c * 4096, pack_bf16(acc[t][4 * c], acc[t][4 * c + 1]), pack_bf16(acc[t][4 * c + 2], acc[t][4 * c + 3]),
              pack_bf16(acc[t][4 * c + 4], acc[t][4 * c + 5]), pack_bf16(acc[t][4 * c + 6], acc[t][4 * c + 7]));
#pragma unroll
    for (int c = 0; c < 4; c += 2)
      stsm4_t(base + t * 49152 + 3072 + (wg * 4 + c) * 4096, pack_bf16(acs[t][4 * c], acs[t][4 * c + 1]), pack_bf16(acs[t][4 * c + 2], acs[t][4 * c + 3]),
              pack_bf16(acs[t][4 * c + 4], acs[t][4 * c + 5]), pack_bf16(acs[t][4 * c + 6], acs[t][4 * c + 7]));
  }
  fence_async();
  named_sync(1, 384);
}

__device__ __forceinline__ int ostage_pos(int j, int w) { return j + (w ? 4 - w : 0); }
__device__ __forceinline__ int ostage_tile(int pos, int w) {
  const int q = pos >> 2;
  return w == 0 ? 3 * q : q == 0 ? 5 + w : 3 * q - 3 + w;
}
__device__ __forceinline__ void oproj_stash(const float (&acc)[48], uint32_t sb, int wg, int st) {
  const int tid = threadIdx.x, mi = (tid & 31) >> 3, r8 = tid & 7;
  const uint32_t base = sb + SM_RING + (st < 29 ? 7 : st % 7) * 16384 + r8 * 128 + (((((tid >> 4) & 6) + (mi & 1)) ^ r8) << 4) + (mi >> 1) * 1024;
  if (st > 1) mbar_wait(sb + SM_BAR + B_SFREE + (st < 29 ? (st >> 2) - 1 : st - 25) * 8, 0);
  if (st >= 29) named_sync(6 + wg, 128);
#pragma unroll
  for (int c = 0; c < 12; c += 2)
    stsm4_t(base + c * 1024, pack_bf16(acc[4 * c], acc[4 * c + 1]), pack_bf16(acc[4 * c + 2], acc[4 * c + 3]),
            pack_bf16(acc[4 * c + 4], acc[4 * c + 5]), pack_bf16(acc[4 * c + 6], acc[4 * c + 7]));
  fence_async();
  named_arrive(9 + wg, 160);
}

__device__ __forceinline__ void oproj(uint32_t sb, int wg) {
  float acc[48];
#pragma unroll 1
  for (int st = wg, j = 0; st < 32; st += 3, j++) {
    const int c = ostage_pos(j, wg) & 3;
    const uint64_t da = mk_desc(SM_RING + (st % 7) * 16384, 0, 1024, 1);
    const uint64_t db = mk_desc(SM_Q + c * 1024, 0, 4096, 1);
    if (threadIdx.x == 256 && j == 0) STAMP(59);
    mbar_wait(sb + SM_BAR + B_WFULL + st * 8, 0);
    wg_fence();
#pragma unroll
    for (int kk = 0; kk < 8; kk++) wgmma_n96_tA(acc, da + kk * 128, db + (kk >> 2) * 3072 + (kk & 3) * 2, kk > 0 || (c > 0 && j > 0));
    wg_commit();
    wg_wait<0>();
    reg_fence(acc);
    if (st < 25 && (threadIdx.x & 31) == 0) mbar_arrive_cta(sb + SM_BAR + B_WEMPTY + (st + 8) * 8, ~st & 1, 1);
    if (c == 3 || st >= 30) oproj_stash(acc, sb, wg, st);
  }
}

__global__ void __cluster_dims__(2, 1, 1) __launch_bounds__(512, 1) gqa_fused_kernel(const __grid_constant__ Params p) {
  extern __shared__ __align__(1024) uint8_t smem_raw[];
  const uint32_t sb = smem_u32(smem_raw);
  if ((sb & 0xFFFFFF) != SM_BASE) return;
  const uint32_t bar = sb + SM_BAR;
  const int tid = threadIdx.x, wg = __shfl_sync(0xffffffffu, tid >> 7, 0), warp = __shfl_sync(0xffffffffu, (tid >> 5) & 3, 0), lane = tid & 31;
  const int bpair = blockIdx.x & 7, hkv = (blockIdx.x >> 3) & 7, blk = blockIdx.x >> 6;
  const int rank = bpair & 1;

  if (tid == 0) STAMP(0);
#pragma unroll
  for (int e = tid; e < PF_EARLY * 32; e += 384)
    if (tid < 384)
      pf_l2((const char*)((e & 256) ? p.vp[blk] : p.kp[blk]) + (size_t)(bpair * 16 + hkv) * 262144 + (e >> 9) * 32768 + (e & 255) * 128);
  if (tid == 384) {
    asm volatile("prefetch.tensormap [%0];" ::"l"(&p.wq[blk]) : "memory");
    asm volatile("prefetch.tensormap [%0];" ::"l"(&p.x[blk]) : "memory");
#pragma unroll
    for (int i = 0; i < NQS; i++) { mbar_init(bar + B_QFULL + i * 8, 1); mbar_init(bar + B_QEMPTY + i * 8, 24); }
    asm volatile("st.volatile.shared.u32 [%0], %1;" ::"r"(bar + B_NLOAD), "r"(0) : "memory");
#pragma unroll
    for (int i = 0; i < 4; i++) { mbar_init(bar + B_FULL + i * 8, 1); mbar_init(bar + B_EMPTY + i * 16, 24); }
    asm volatile("fence.mbarrier_init.release.cluster;" ::: "memory");
  }
  if (tid == 416) {
#pragma unroll
    for (int i = 0; i < 32; i++) { mbar_init(bar + B_WFULL + i * 8, 1); mbar_init(bar + B_WEMPTY + i * 8, i < 8 ? 12 : 8); }
    mbar_init(bar + B_WEMPTY + 256, 8);
#pragma unroll
    for (int i = 0; i < 7; i++) mbar_init(bar + B_SFREE + i * 8, 1);
    asm volatile("fence.mbarrier_init.release.cluster;" ::: "memory");
  }
  __syncwarp();
  asm volatile("barrier.cluster.arrive.relaxed.aligned;" ::: "memory");
  if (tid >= 416 && tid < 448) mbar_expect_tx(bar + B_WFULL + lane * 8, 16384);
  if (tid == 448) {
    asm volatile("prefetch.tensormap [%0];" ::"l"(&p.mo) : "memory");
    asm volatile("prefetch.tensormap [%0];" ::"l"(&p.k[blk]) : "memory");
    asm volatile("prefetch.tensormap [%0];" ::"l"(&p.v[blk]) : "memory");
    asm volatile("prefetch.tensormap [%0];" ::"l"(&p.wo[blk]) : "memory");
  }
  __syncwarp();
  asm volatile("barrier.cluster.wait.aligned;" ::: "memory");

  if (wg == 3) {
    asm volatile("setmaxnreg.dec.sync.aligned.u32 32;");
    if (warp == 2) {
      wait_nload(bar, CLR_N);
      __nv_bfloat16* o = p.out + (size_t)(bpair * 96 + (lane >> 3)) * 1024 + blk * 512 + hkv * 64 + (lane & 7) * 8;
#pragma unroll 4
      for (int i = 0; i < 24; i++) *reinterpret_cast<uint4*>(o + i * 4096) = make_uint4(0, 0, 0, 0);
      __threadfence();
      __syncwarp();
      if (lane == 0) {
        unsigned int* cnt = g_cleared + blk * 8 + bpair;
        unsigned int old, cur;
        asm volatile("atom.acq_rel.gpu.global.add.u32 %0, [%1], 1;" : "=r"(old) : "l"(cnt) : "memory");
        const unsigned int target = (old & ~7u) + 8;
        int it = 0;
        do {
          __nanosleep(500);
          asm volatile("ld.acquire.gpu.global.u32 %0, [%1];" : "=r"(cur) : "l"(cnt) : "memory");
        } while ((int)(cur - target) < 0 && ++it < 100000);
        asm volatile("fence.proxy.async;" ::: "memory");
      }
      for (int i = 0; i < 10; i++) {
        const int st = i < 8 ? 4 * i + 1 : 22 + i, w = st % 3;
        named_sync(9 + w, 160);
        if (lane == 0) {
          asm volatile("cp.reduce.async.bulk.tensor.2d.global.shared::cta.add.tile.bulk_group [%0, {%1, %2}], [%3];"
                       ::"l"(&p.mo), "r"(blk * 512 + ((hkv + ostage_tile(ostage_pos(st / 3, w), w)) & 7) * 64), "r"(bpair * 96),
                       "r"(sb + SM_RING + (st < 29 ? 7 : st % 7) * 16384) : "memory");
          asm volatile("cp.async.bulk.commit_group;" ::: "memory");
          if (i < 7) {
            asm volatile("cp.async.bulk.wait_group.read 0;" ::: "memory");
            mbar_arrive_local(bar + B_SFREE + i * 8, 1);
          }
        }
        __syncwarp();
      }
      if (lane == 0) asm volatile("cp.async.bulk.wait_group 0;" ::: "memory");
      if (lane == 0) STAMP(6);
    }
    if (warp == 1) {
      const char* wq = (const char*)(p.wqp[blk] + hkv * 512 + (size_t)(bpair + (lane >> 3) * 8) * 4096) + (lane & 7) * 128;
      const char* xs = (const char*)(p.xp[blk] + (size_t)(bpair * 96 + hkv * 12) * 512);
      const char* wo = (const char*)(p.wop[blk] + (size_t)(hkv * 512 + bpair * 64) * 512);
      const size_t kvo = (size_t)(bpair * 16 + hkv) * 262144 + lane * 128;
      uint32_t tn = gtime() + PF_T0;
      for (int i = 4; i < 16; i++) {
        wait_until(tn);
        const int e = (i - 4) * 32 + lane;
        if (i >= 6) pf_l2(wq + (size_t)i * 262144);
        else if (e < 60) pf_l2(xs + (e / 5) * 1024 + (3 + e % 5) * 128);
        tn += PF_DT0;
      }
      for (int j = PF_EARLY; j < 8 * PF_NKV; j++) {
        wait_until(tn);
        uint32_t nl;
        asm volatile("ld.volatile.shared.u32 %0, [%1];" : "=r"(nl) : "r"(bar + B_NLOAD) : "memory");
        if (j < (int)nl * 8) j = nl * 8;
        const int n = j >> 3;
        if (n >= PF_NKV) break;
        const char* a = (const char*)((n & 1) ? p.vp[blk] : p.kp[blk]) + kvo + (n >> 4) * 2097152 + ((n >> 1) & 7) * 32768 + (j & 7) * 4096;
        pf_l2(a);
        tn += PF_DT;
      }
      wait_nload(bar, 32);
      mbar_wait(bar + B_FULL + 24, 1);
      tn = gtime();
      for (int i = 0; i < 16; i++) {
        wait_until(tn);
        pf_l2(wo + ((i & 3) * 16 + (lane >> 1)) * 1024 + ((hkv + (i >> 2) * 2 + (lane & 1)) & 7) * 128);
        tn += WO_DT;
      }
    }
    if (warp == 0 && lane == 0) {
      uint64_t pol;
      asm volatile("createpolicy.fractional.L2::evict_first.b64 %0, 1.0;" : "=l"(pol));
      const int row0 = (bpair * 16 + hkv) * 1024;
      uint32_t tnext = gtime() + PACE_T0 + ((blockIdx.x >> 1) & 7) * PACE_ST;
      STAMP(7);
      int slot = 1, par = 1;
      for (int s = 0; s < 32; s++) {
        mbar_wait(bar + B_QEMPTY + slot * 8, par);
        const uint32_t fb = bar + B_QFULL + slot * 8;
        mbar_expect_tx(fb, QSTAGE);
        tma3d_mc(sb + (slot < 8 ? SM_RING : SM_Q - 131072) + slot * 16384 + rank * 8192, &p.wq[blk], 0, s * 16, hkv * 8 + rank * 4, fb);
        tma2d(sb + SM_XQ + slot * 3072, &p.x[blk], s * 16, bpair * 96, fb);
        if (++slot == NQS) slot = 0;
        if (slot == 1) par ^= 1;
      }
      for (int n = 0; n < 32; n++) {
        const int slot = n & 3;
        if (n < 4) {
          mbar_wait(bar + B_QEMPTY + n * 16, n == 0);
          mbar_wait(bar + B_QEMPTY + n * 16 + 8, 0);
        } else {
          mbar_wait(bar + B_EMPTY + slot * 16, ((n >> 2) & 1) ^ 1);
        }
        if (n >= 4) {
          wait_until(tnext);
          tnext += PACE_DT;
        }
        const uint32_t fb = bar + B_FULL + slot * 8;
        asm volatile("st.volatile.shared.u32 [%0], %1;" ::"r"(bar + B_NLOAD), "r"(n + 1) : "memory");
        mbar_expect_tx(fb, 32768);
        const int row = row0 + (n >> 4) * 8192 + ((n >> 1) & 7) * 128;
        tma3d_hint(sb + SM_RING + slot * 32768, (n & 1) ? &p.v[blk] : &p.k[blk], 0, row, 0, fb, pol);
      }
      for (int i = 0; i < 32; i += (i < 6 ? 1 : i == 6 ? 2 - rank : 2)) {
        mbar_wait(bar + B_WEMPTY + (i + (i >= 7)) * 8, 0);
        const int pos = ostage_pos(i / 3, i % 3), ti = ostage_tile(pos, i % 3), c = pos & 3;
        const uint32_t dst = sb + SM_RING + (i % 7) * 16384;
        const int c0 = ((hkv + ti) & 7) * 64, c1 = hkv * 512 + c * 128;
        if (i < 7) tma2d(dst, &p.wo[blk], c0, c1, bar + B_WFULL + i * 8);
        else tma2d_mc(dst, &p.wo[blk], c0, c1, bar + B_WFULL + i * 8);
      }
    }
  } else {
    asm volatile("setmaxnreg.inc.sync.aligned.u32 160;");
    qproj(sb, wg, warp, lane);
    if (tid == 0) STAMP(1);

    const float cs = 0.08838834764831845f * 1.4426950408889634f;
    uint32_t ebase = lane < 2 ? bar + B_EMPTY : 0;
    float o[64];
#pragma unroll
    for (int i = 0; i < 64; i++) o[i] = 0.f;
    float m0 = -INFINITY, m1 = -INFINITY, l0 = 0.f, l1 = 0.f;
#pragma unroll 1
    for (int t = 0; t < 16; t++) {
      {
        const int ks = (t & 1) * 2;
        const uint64_t dq = mk_desc(SM_Q + (t >> 3) * 24576 + wg * 8192, 0, 1024, 1);
        if (t == 14 && ebase) ebase += B_WEMPTY - B_EMPTY + (threadIdx.x & 1) * 8;
        float s[64];
        const uint64_t dk = mk_desc(SM_RING + ks * 32768, 0, 1024, 1);
        mbar_wait(sb + SM_BAR + B_FULL + ks * 8, (t >> 1) & 1);
        if (wg == 1 || (wg == 0) == (t != 0)) named_sync(3 + wg, 256);
        wg_fence();
#pragma unroll
        for (int kk = 0; kk < 8; kk++)
          wgmma_n128_ss(s, dq + (kk >> 2) * 3072 + (kk & 3) * 2, dk + (kk >> 2) * 1024 + (kk & 3) * 2, kk > 0);
        wg_commit();
        named_arrive(wg == 2 ? 3 : 4 + wg, 256);
        wg_wait<0>();
        reg_fence(s);
        if (ebase) mbar_arrive_local(ebase + ks * 16, 1);

        float xa = fmaxf(s[0], m0), xb = s[1], xc = fmaxf(s[2], m1), xd = s[3];
#pragma unroll
        for (int c = 1; c < 16; c++) {
          xa = fmaxf(xa, s[4 * c]); xb = fmaxf(xb, s[4 * c + 1]);
          xc = fmaxf(xc, s[4 * c + 2]); xd = fmaxf(xd, s[4 * c + 3]);
        }
        float mn0 = fmaxf(xa, xb), mn1 = fmaxf(xc, xd);
        mn0 = fmaxf(mn0, __shfl_xor_sync(0xffffffffu, mn0, 1));
        mn1 = fmaxf(mn1, __shfl_xor_sync(0xffffffffu, mn1, 1));
        mn0 = fmaxf(mn0, __shfl_xor_sync(0xffffffffu, mn0, 2));
        mn1 = fmaxf(mn1, __shfl_xor_sync(0xffffffffu, mn1, 2));
        const float nb0 = -mn0 * cs, nb1 = -mn1 * cs;
        const float sc0 = ex2v(fmaf(m0, cs, nb0)), sc1 = ex2v(fmaf(m1, cs, nb1));
        m0 = mn0; m1 = mn1;
        uint32_t pr[32];
        float e0 = ex2v(fmaf(s[0], cs, nb0)), e1 = ex2v(fmaf(s[1], cs, nb0));
        float e2 = ex2v(fmaf(s[2], cs, nb1)), e3 = ex2v(fmaf(s[3], cs, nb1));
        l0 *= sc0; l1 *= sc1;
        float l2 = 0.f, l3 = 0.f;
#pragma unroll
        for (int c = 0; c < 16; c++) {
          float f0, f1, f2, f3;
          if (c < 15) {
            f0 = ex2v(fmaf(s[4 * c + 4], cs, nb0)); f1 = ex2v(fmaf(s[4 * c + 5], cs, nb0));
            f2 = ex2v(fmaf(s[4 * c + 6], cs, nb1)); f3 = ex2v(fmaf(s[4 * c + 7], cs, nb1));
          }
          mulv(o[4 * c], sc0); mulv(o[4 * c + 1], sc0);
          mulv(o[4 * c + 2], sc1); mulv(o[4 * c + 3], sc1);
          l0 += e0; l2 += e1; l1 += e2; l3 += e3;
          pr[2 * c] = pack_bf16(e0, e1);
          pr[2 * c + 1] = pack_bf16(e2, e3);
          e0 = f0; e1 = f1; e2 = f2; e3 = f3;
        }
        l0 += l2; l1 += l3;
        reg_fence(o);
        const int vs = (t & 1) * 2 + 1;
        const uint64_t dv = mk_desc(SM_RING + vs * 32768, 16384, 1024, 1);
        mbar_wait(sb + SM_BAR + B_FULL + vs * 8, (t >> 1) & 1);
        reg_fence(o);
        named_sync(3 + wg, 256);
        wg_fence();
#pragma unroll
        for (int kk = 0; kk < 8; kk++)
          wgmma_n128_rs_tB(o, pr[4 * kk], pr[4 * kk + 1], pr[4 * kk + 2], pr[4 * kk + 3], dv + kk * 128, kk > 0 || (t & 7) != 0);
        wg_commit();
        if (wg != 2) named_arrive(wg == 0 ? 4 : t == 15 ? 5 : 3, 256);
        wg_wait<0>();
        reg_fence(o);
        if (ebase) mbar_arrive_local(ebase + vs * 16, 1);
        if (tid == 0 && (t & 3) == 3) STAMP(8 + t);
      }
      if ((t & 7) == 7) {
        l0 += __shfl_xor_sync(0xffffffffu, l0, 1);
        l1 += __shfl_xor_sync(0xffffffffu, l1, 1);
        l0 += __shfl_xor_sync(0xffffffffu, l0, 2);
        l1 += __shfl_xor_sync(0xffffffffu, l1, 2);
        const float i0 = 1.f / l0, i1 = 1.f / l1;
        const int ln = threadIdx.x & 31, mi = ln >> 3, r8 = ln & 7;
        const uint32_t obase = sb + SM_Q + (t >> 3) * 24576 + wg * 8192 + (((threadIdx.x >> 5) & 3) * 16 + (mi & 1) * 8 + r8) * 128;
#pragma unroll
        for (int c = 0; c < 16; c += 2) {
          const int ch = (c & 7) + (mi >> 1);
          stsm4(obase + (c >> 3) * 49152 + ((ch ^ r8) << 4),
                pack_bf16(o[4 * c] * i0, o[4 * c + 1] * i0), pack_bf16(o[4 * c + 2] * i1, o[4 * c + 3] * i1),
                pack_bf16(o[4 * c + 4] * i0, o[4 * c + 5] * i0), pack_bf16(o[4 * c + 6] * i1, o[4 * c + 7] * i1));
        }
        m0 = m1 = -INFINITY;
        l0 = l1 = 0.f;
      }
    }
    fence_async();
    named_sync(1, 384);

    oproj(sb, wg);
    if ((tid & 127) == 0) STAMP(3 + wg);
  }
}

typedef CUresult (*EncodeFn)(CUtensorMap*, CUtensorMapDataType, cuuint32_t, void*, const cuuint64_t*, const cuuint64_t*,
                             const cuuint32_t*, const cuuint32_t*, CUtensorMapInterleave, CUtensorMapSwizzle,
                             CUtensorMapL2promotion, CUtensorMapFloatOOBfill);

void encode(EncodeFn enc, CUtensorMap* m, const void* ptr, int rank, const cuuint64_t* dims, const cuuint64_t* strides,
            const cuuint32_t* box, CUtensorMapSwizzle sw) {
  cuuint32_t es[3] = {1, 1, 1};
  enc(m, CU_TENSOR_MAP_DATA_TYPE_BFLOAT16, rank, const_cast<void*>(ptr), dims, strides, box, es, CU_TENSOR_MAP_INTERLEAVE_NONE, sw,
      CU_TENSOR_MAP_L2_PROMOTION_L2_128B, CU_TENSOR_MAP_FLOAT_OOB_FILL_NONE);
}

}

extern "C" void kernel_launch(void* const* d_in, const int* in_sizes, int n_in, void* d_out, int out_size) {
  (void)in_sizes; (void)n_in; (void)out_size;
  static EncodeFn enc = nullptr;
  if (!enc) {
    cudaDriverEntryPointQueryResult qr;
    cudaGetDriverEntryPoint("cuTensorMapEncodeTiled", (void**)&enc, cudaEnableDefault, &qr);
    cudaFuncSetAttribute(gqa_fused_kernel, cudaFuncAttributeMaxDynamicSharedMemorySize, SMEM_BYTES);
  }
  Params p;
  for (int b = 0; b < 2; b++) {
    const void* x = d_in[b * 5 + 0];
    const void* k = d_in[b * 5 + 1];
    const void* v = d_in[b * 5 + 2];
    const void* wq = d_in[b * 5 + 3];
    const void* wo = d_in[b * 5 + 4];
    {
      cuuint64_t d[2] = {512, 768}, s[1] = {1024};
      cuuint32_t bx[2] = {16, 96};
      encode(enc, &p.x[b], x, 2, d, s, bx, CU_TENSOR_MAP_SWIZZLE_32B);
    }
    {
      cuuint64_t d[3] = {64, 131072, 2}, s[2] = {256, 128};
      cuuint32_t bx[3] = {64, 128, 2};
      encode(enc, &p.k[b], k, 3, d, s, bx, CU_TENSOR_MAP_SWIZZLE_128B);
      encode(enc, &p.v[b], v, 3, d, s, bx, CU_TENSOR_MAP_SWIZZLE_128B);
    }
    {
      cuuint64_t d[3] = {64, 512, 64}, s[2] = {8192, 128};
      cuuint32_t bx[3] = {64, 16, 4};
      encode(enc, &p.wq[b], wq, 3, d, s, bx, CU_TENSOR_MAP_SWIZZLE_128B);
    }
    {
      cuuint64_t d[2] = {512, 4096}, s[1] = {1024};
      cuuint32_t bx[2] = {64, 128};
      encode(enc, &p.wo[b], wo, 2, d, s, bx, CU_TENSOR_MAP_SWIZZLE_128B);
    }
    p.xp[b] = (const __nv_bfloat16*)x;
    p.wqp[b] = (const __nv_bfloat16*)wq;
    p.wop[b] = (const __nv_bfloat16*)wo;
    p.kp[b] = (const __nv_bfloat16*)k;
    p.vp[b] = (const __nv_bfloat16*)v;
  }
  {
    cuuint64_t d[2] = {1024, 768}, s[1] = {2048};
    cuuint32_t bx[2] = {64, 96};
    encode(enc, &p.mo, d_out, 2, d, s, bx, CU_TENSOR_MAP_SWIZZLE_128B);
  }
  p.out = (__nv_bfloat16*)d_out;
  gqa_fused_kernel<<<128, 512, SMEM_BYTES, cudaStreamPerThread>>>(p);
}
```
